```python
import torch

def _softmax(x, axis=-1):
    return torch.softmax(x, dim=axis)
def _gelu(x):
    return torch.nn.functional.gelu(x, approximate="tanh")
def _silu(x):
    return torch.nn.functional.silu(x)
def _sigmoid(x):
    return torch.sigmoid(x)
def _layernorm(x, axis=-1, eps=1e-5):
    m = x.mean(dim=axis, keepdim=True)
    v = x.var(dim=axis, keepdim=True, unbiased=False)
    return (x - m) / torch.sqrt(v + eps)
def _scatter_add(tgt, idx, src, axis=0):
    return tgt.clone().index_add_(axis, idx, src)
def _segment_sum(src, seg, n):
    out = torch.zeros((n,) + src.shape[1:], dtype=src.dtype)
    return out.index_add_(0, seg, src)
def _pad(x, pw):
    flat = tuple(v for pair in reversed(pw) for v in pair)
    return torch.nn.functional.pad(x, flat)

kernel_name = 'parallel_sum__linear_attn_block__glu_gated_bilinear__prompt'

def setup_inputs():

    _w = (lambda a: (lambda t: t.to(torch.bfloat16) if t.is_floating_point() else t)(torch.as_tensor(a)))
    def _A_setup():
        B, S, D = 1, 2048, 512
        return {
            "x": _w((lambda *s: torch.randn(*s, dtype=torch.bfloat16) * 0.05)(B, S, D)),
            "wqkv": _w((lambda *s: torch.randn(*s, dtype=torch.bfloat16) * 0.05)(D, 3 * D)),
            "wo": _w((lambda *s: torch.randn(*s, dtype=torch.bfloat16) * 0.05)(D, D)),
        }
    _A_in = _A_setup()

    def _B_setup():
        B, S, D, F = 1, 2048, 512, 1792
        return {
            "x": _w((lambda *s: torch.randn(*s, dtype=torch.bfloat16) * 0.05)(B, S, D)),
            "w_gate": _w((lambda *s: torch.randn(*s, dtype=torch.bfloat16) * 0.2)(D, F) * (D ** -0.5)),
            "w_up": _w((lambda *s: torch.randn(*s, dtype=torch.bfloat16) * 0.2)(D, F) * (D ** -0.5)),
            "w_down": _w((lambda *s: torch.randn(*s, dtype=torch.bfloat16) * 0.2)(F, D) * (F ** -0.5)),
        }
    _B_in = _B_setup()

    return {
        "A_x": _A_in["x"],
        "A_wqkv": _A_in["wqkv"],
        "A_wo": _A_in["wo"],
        "B_x": _B_in["x"],
        "B_w_gate": _B_in["w_gate"],
        "B_w_up": _B_in["w_up"],
        "B_w_down": _B_in["w_down"],
    }

def reference(A_x, A_wqkv, A_wo, B_x, B_w_gate, B_w_up, B_w_down):
    def _A_ref(x, wqkv, wo):
        B, S, D = x.shape
        H = 32; Dh = D // H
        qkv = (lambda x, *d: x.permute(*d))((x @ wqkv).reshape(B, S, 3, H, Dh), 2, 0, 3, 1, 4)
        q, k, v = qkv[0], qkv[1], qkv[2]
        phi = lambda t: torch.where(t > 0, t + 1, torch.exp(t)) + 1e-6
        pq, pk = phi(q), phi(k)
        kv = torch.einsum("bhsd,bhse->bhde", pk, v)
        z = torch.einsum("bhsd->bhd", pk)
        num = torch.einsum("bhqd,bhde->bhqe", pq, kv)
        den = torch.einsum("bhqd,bhd->bhq", pq, z)[..., None] + 1e-6
        o = num / den
        return (lambda x, *d: x.permute(*d))(o, 0, 2, 1, 3).reshape(B, S, D) @ wo

    def _B_ref(x, w_gate, w_up, w_down):
        g = torch.einsum("bsd,df->bsf", x, w_gate)
        u = torch.einsum("bsd,df->bsf", x, w_up)
        h = g * u
        return torch.einsum("bsf,fd->bsd", h, w_down)

    x = A_x
    xn = _layernorm(x, axis=-1)
    return x + _A_ref(xn, A_wqkv, A_wo) + _B_ref(xn, B_w_gate, B_w_up, B_w_down)
```

```cpp
#include <cuda_runtime.h>
#include <cuda_bf16.h>
#include <cuda.h>
#include <stdint.h>
#include <stdio.h>

namespace {

constexpr int SEQ = 2048, DM = 512, FF = 1792, KH = 2304;
constexpr int NSLOT = 12;
constexpr uint32_t SLOT_BYTES = 16384;
constexpr uint32_t OFF_STG = NSLOT * SLOT_BYTES;
constexpr uint32_t OFF_BAR = OFF_STG + 32768;
constexpr uint32_t BAR_FULL = OFF_BAR, BAR_EMPTY = OFF_BAR + 96, BAR_STG_FULL = OFF_BAR + 192, BAR_STG_EMPTY = OFF_BAR + 208,
                   BAR_KVI = OFF_BAR + 224, BAR_PEER = OFF_BAR + 240, BAR_XCH = OFF_BAR + 248, BAR_XR = OFF_BAR + 256;
constexpr uint32_t OFF_ONES = OFF_BAR + 512;
constexpr uint32_t SMEM_BYTES = OFF_ONES + 2048;
constexpr uint32_t SM0 = 1024;
constexpr int NUM_CTAS = 132;
constexpr int SPIN_LIMIT = 1 << 21;
constexpr int ASYM = 2;
constexpr int LEAD = 2;
constexpr int NSHARED = 18 - ASYM, NSTAGE = 18 + ASYM;

struct Scratch {
    uint32_t epoch[32];
    uint32_t hflag[32 * 32];
    uint32_t kvflag[8 * 32];
    uint32_t kviflag[8 * 32];
    uint32_t kvi[32 * 192];
    float zp[8 * 16 * 64];
    float4 kvp[8 * 16 * 4 * 64];
};
__device__ __align__(1024) Scratch g_scr;
__device__ __align__(1024) __nv_bfloat16 g_H[SEQ * KH];

struct Params {
    const __nv_bfloat16* x;
    Scratch* scr;
    __nv_bfloat16* outp;
    const __nv_bfloat16* wd_ptr;
    const __nv_bfloat16* wo_ptr;
    CUtensorMap wqkv;
    CUtensorMap wg, wu, wd, wo;
    CUtensorMap h128;
    CUtensorMap h64;
    CUtensorMap x2;
    CUtensorMap wq32, wg32, wu32, h32;
};

__device__ __forceinline__ uint32_t smem_u32(const void* p) { return (uint32_t)__cvta_generic_to_shared(p); }
__device__ __forceinline__ int lane_id() { int l; asm volatile("mov.u32 %0, %%laneid;" : "=r"(l)); return l; }
__device__ __forceinline__ bool elect_one() {
    uint32_t p;
    asm volatile("{\n.reg .pred P;\nelect.sync _|P, 0xffffffff;\nselp.u32 %0, 1, 0, P;\n}" : "=r"(p));
    return p != 0;
}
__device__ __forceinline__ void spin_guard(int it) {
    asm volatile("{\n.reg .pred p;\nsetp.gt.s32 p, %0, %1;\n@p trap;\n}" :: "r"(it), "n"(SPIN_LIMIT));
}
__device__ __forceinline__ void mbar_init(uint32_t bar, uint32_t cnt) { asm volatile("mbarrier.init.shared::cta.b64 [%0], %1;" :: "r"(bar), "r"(cnt) : "memory"); }
__device__ __forceinline__ void mbar_expect_tx(uint32_t bar, uint32_t bytes) { asm volatile("mbarrier.arrive.expect_tx.shared::cta.b64 _, [%0], %1;" :: "r"(bar), "r"(bytes) : "memory"); }
__device__ __forceinline__ void mbar_arrive(uint32_t bar) { asm volatile("mbarrier.arrive.shared::cta.b64 _, [%0];" :: "r"(bar) : "memory"); }
__device__ __forceinline__ void mbar_arrive2(uint32_t bar) { asm volatile("mbarrier.arrive.shared::cta.b64 _, [%0], 2;" :: "r"(bar) : "memory"); }
__device__ __forceinline__ bool mbar_test(uint32_t bar, uint32_t parity) {
    uint32_t ok;
    asm volatile("{\n.reg .pred p;\nmbarrier.test_wait.parity.shared::cta.b64 p, [%1], %2;\nselp.u32 %0, 1, 0, p;\n}" : "=r"(ok) : "r"(bar), "r"(parity) : "memory");
    return ok != 0;
}
__device__ __forceinline__ void mbar_wait(uint32_t bar, uint32_t parity) {
    asm volatile("{\n.reg .pred P1;\n.reg .u32 cnt;\nmov.u32 cnt, 0;\n"
                 "LAB_WAIT:\nmbarrier.try_wait.parity.shared::cta.b64 P1, [%0], %1;\n@P1 bra DONE;\n"
                 "add.u32 cnt, cnt, 1;\nsetp.lt.u32 P1, cnt, %2;\n@P1 bra LAB_WAIT;\ntrap;\n"
                 "DONE:\n}" :: "r"(bar), "r"(parity), "n"(SPIN_LIMIT) : "memory");
}
__device__ __forceinline__ void tma_ld2(uint32_t dst, const CUtensorMap* m, uint32_t bar, int c0, int c1) {
    asm volatile("cp.async.bulk.tensor.2d.shared::cluster.global.mbarrier::complete_tx::bytes [%0], [%1, {%3, %4}], [%2];"
                 :: "r"(dst), "l"(m), "r"(bar), "r"(c0), "r"(c1) : "memory");
}
__device__ __forceinline__ void tma_st2(const CUtensorMap* m, uint32_t src, int c0, int c1) {
    asm volatile("cp.async.bulk.tensor.2d.global.shared::cta.bulk_group [%0, {%2, %3}], [%1];" :: "l"(m), "r"(src), "r"(c0), "r"(c1) : "memory");
}
__device__ __forceinline__ void bulk_ld(uint32_t dst, const void* src, uint32_t bytes, uint32_t bar) {
    asm volatile("cp.async.bulk.shared::cluster.global.mbarrier::complete_tx::bytes [%0], [%1], %2, [%3];" :: "r"(dst), "l"(src), "r"(bytes), "r"(bar) : "memory");
}
__device__ __forceinline__ void prefetch_map(const CUtensorMap* m) { asm volatile("prefetch.tensormap [%0];" :: "l"(m) : "memory"); }
__device__ __forceinline__ void bulk_commit() { asm volatile("cp.async.bulk.commit_group;" ::: "memory"); }
__device__ __forceinline__ void bulk_wait0() { asm volatile("cp.async.bulk.wait_group 0;" ::: "memory"); }
__device__ __forceinline__ void fence_async_smem() { asm volatile("fence.proxy.async.shared::cta;" ::: "memory"); }
__device__ __forceinline__ void fence_async_global() { asm volatile("fence.proxy.async.global;" ::: "memory"); }
__device__ __forceinline__ void bar_sync(int id, int n) { asm volatile("bar.sync %0, %1;" :: "r"(id), "r"(n) : "memory"); }
__device__ __forceinline__ void bar_arrive(int id, int n) { asm volatile("bar.arrive %0, %1;" :: "r"(id), "r"(n) : "memory"); }
__device__ __forceinline__ uint32_t ld_relaxed(const uint32_t* p) { uint32_t v; asm volatile("ld.relaxed.gpu.global.u32 %0, [%1];" : "=r"(v) : "l"(p) : "memory"); return v; }
__device__ __forceinline__ void red_release(uint32_t* p, uint32_t v) { asm volatile("red.release.gpu.global.add.u32 [%0], %1;" :: "l"(p), "r"(v) : "memory"); }
__device__ __forceinline__ void wait_flag(const uint32_t* p, uint32_t target) {
    asm volatile("{\n.reg .pred P1;\n.reg .u32 cnt, v;\nmov.u32 cnt, 0;\n"
                 "LAB_WAIT:\nld.acquire.gpu.global.u32 v, [%0];\nsub.u32 v, v, %1;\nsetp.ge.s32 P1, v, 0;\n@P1 bra DONE;\n"
                 "add.u32 cnt, cnt, 1;\nsetp.lt.u32 P1, cnt, %2;\n@P1 bra LAB_WAIT;\ntrap;\n"
                 "DONE:\n}" :: "l"(p), "r"(target), "n"(SPIN_LIMIT) : "memory");
    __syncwarp();
}
__device__ __forceinline__ void wg_fence() { asm volatile("wgmma.fence.sync.aligned;" ::: "memory"); }
__device__ __forceinline__ void wg_commit() { asm volatile("wgmma.commit_group.sync.aligned;" ::: "memory"); }
template <int N> __device__ __forceinline__ void wg_wait() { asm volatile("wgmma.wait_group.sync.aligned %0;" :: "n"(N) : "memory"); }
__device__ __forceinline__ void ldsm4(uint32_t& r0, uint32_t& r1, uint32_t& r2, uint32_t& r3, uint32_t addr) {
    asm volatile("ldmatrix.sync.aligned.m8n8.x4.shared.b16 {%0,%1,%2,%3}, [%4];" : "=r"(r0), "=r"(r1), "=r"(r2), "=r"(r3) : "r"(addr) : "memory");
}
__device__ __forceinline__ void stsm4(uint32_t addr, uint32_t r0, uint32_t r1, uint32_t r2, uint32_t r3) {
    asm volatile("stmatrix.sync.aligned.m8n8.x4.shared.b16 [%0], {%1,%2,%3,%4};" :: "r"(addr), "r"(r0), "r"(r1), "r"(r2), "r"(r3) : "memory");
}
__device__ __forceinline__ void mma16816(float* d, uint32_t a0, uint32_t a1, uint32_t a2, uint32_t a3, uint32_t b0, uint32_t b1) {
    asm volatile("mma.sync.aligned.m16n8k16.row.col.f32.bf16.bf16.f32 {%0,%1,%2,%3}, {%4,%5,%6,%7}, {%8,%9}, {%0,%1,%2,%3};"
                 : "+f"(d[0]), "+f"(d[1]), "+f"(d[2]), "+f"(d[3]) : "r"(a0), "r"(a1), "r"(a2), "r"(a3), "r"(b0), "r"(b1));
}
__device__ __forceinline__ uint32_t hadd2(uint32_t a, uint32_t b) { uint32_t r; asm("add.rn.bf16x2 %0, %1, %2;" : "=r"(r) : "r"(a), "r"(b)); return r; }
__device__ __forceinline__ uint32_t hmul2(uint32_t a, uint32_t b) { uint32_t r; asm("mul.rn.bf16x2 %0, %1, %2;" : "=r"(r) : "r"(a), "r"(b)); return r; }
__device__ __forceinline__ void fence16(uint32_t* v) {
    asm volatile("" : "+r"(v[0]), "+r"(v[1]), "+r"(v[2]), "+r"(v[3]), "+r"(v[4]), "+r"(v[5]), "+r"(v[6]), "+r"(v[7]), "+r"(v[8]), "+r"(v[9]), "+r"(v[10]),
                      "+r"(v[11]), "+r"(v[12]), "+r"(v[13]), "+r"(v[14]), "+r"(v[15]));
}
__device__ __forceinline__ uint32_t pack2(float lo, float hi) {
    uint32_t r; asm("cvt.rn.bf16x2.f32 %0, %1, %2;" : "=r"(r) : "f"(hi), "f"(lo)); return r;
}
__device__ __forceinline__ float bf_lo(uint32_t v) { return __uint_as_float(v << 16); }
__device__ __forceinline__ float bf_hi(uint32_t v) { return __uint_as_float(v & 0xffff0000u); }
__device__ __forceinline__ uint32_t hfma2(uint32_t a, uint32_t b, uint32_t c) {
    uint32_t r; asm("fma.rn.bf16x2 %0, %1, %2, %3;" : "=r"(r) : "r"(a), "r"(b), "r"(c)); return r;
}
__device__ __forceinline__ float ex2(float t) { float r; asm("ex2.approx.ftz.f32 %0, %1;" : "=f"(r) : "f"(t)); return r; }
__device__ __forceinline__ float rcp(float t) { float r; asm("rcp.approx.ftz.f32 %0, %1;" : "=f"(r) : "f"(t)); return r; }
__device__ __forceinline__ float phi(float t) {
    const float a = t * 0.7213475204444817f;
    return fmaf(a + fabsf(a), 0.6931471805599453f, ex2(a - fabsf(a))) + 1e-6f;
}

__device__ __forceinline__ void cp_async16(uint32_t dst, const void* src) { asm volatile("cp.async.cg.shared.global [%0], [%1], 16;" :: "r"(dst), "l"(src) : "memory"); }
__device__ __forceinline__ void cp_commit() { asm volatile("cp.async.commit_group;" ::: "memory"); }
template <int N> __device__ __forceinline__ void cp_wait() { asm volatile("cp.async.wait_group %0;" :: "n"(N) : "memory"); }
__device__ __forceinline__ uint32_t map_peer(uint32_t addr, uint32_t rank) {
    uint32_t r; asm volatile("mapa.shared::cluster.u32 %0, %1, %2;" : "=r"(r) : "r"(addr), "r"(rank)); return r;
}
__device__ __forceinline__ void st_async4(uint32_t addr, uint32_t a, uint32_t b, uint32_t c, uint32_t d, uint32_t bar) {
    asm volatile("st.async.weak.shared::cluster.mbarrier::complete_tx::bytes.v4.b32 [%0], {%1,%2,%3,%4}, [%5];"
                 :: "r"(addr), "r"(a), "r"(b), "r"(c), "r"(d), "r"(bar) : "memory");
}
__device__ __forceinline__ void mbar_wait_cluster(uint32_t bar, uint32_t parity) {
    asm volatile("{\n.reg .pred P1;\n.reg .u32 cnt;\nmov.u32 cnt, 0;\n"
                 "LAB_WAIT:\nmbarrier.try_wait.parity.acquire.cluster.shared::cta.b64 P1, [%0], %1;\n@P1 bra DONE;\n"
                 "add.u32 cnt, cnt, 1;\nsetp.lt.u32 P1, cnt, %2;\n@P1 bra LAB_WAIT;\ntrap;\n"
                 "DONE:\n}" :: "r"(bar), "r"(parity), "n"(SPIN_LIMIT) : "memory");
}

constexpr uint32_t DESC_HI = (1024u >> 4) | (1u << 30);
__device__ __forceinline__ uint64_t desc_b(uint32_t off, uint32_t lbo = 8192) {
    return ((uint64_t)DESC_HI << 32) | (((SM0 + off) >> 4) + ((lbo >> 4) << 16));
}
__device__ __forceinline__ uint64_t desc_a(uint32_t off) {
    return ((uint64_t)DESC_HI << 32) | (((SM0 + off) >> 4) + (1u << 16));
}

#define ACC8(a, o) "+f"(a[o+0]), "+f"(a[o+1]), "+f"(a[o+2]), "+f"(a[o+3]), "+f"(a[o+4]), "+f"(a[o+5]), "+f"(a[o+6]), "+f"(a[o+7])
#define ACC32(a, o) ACC8(a, o), ACC8(a, o+8), ACC8(a, o+16), ACC8(a, o+24)
#define OUT8(a, o) "=f"(a[o+0]), "=f"(a[o+1]), "=f"(a[o+2]), "=f"(a[o+3]), "=f"(a[o+4]), "=f"(a[o+5]), "=f"(a[o+6]), "=f"(a[o+7])
#define OUT32(a, o) OUT8(a, o), OUT8(a, o+8), OUT8(a, o+16), OUT8(a, o+24)
#define REG64 "{%0,%1,%2,%3,%4,%5,%6,%7,%8,%9,%10,%11,%12,%13,%14,%15,%16,%17,%18,%19,%20,%21,%22,%23,%24,%25,%26,%27,%28,%29,%30,%31," \
              "%32,%33,%34,%35,%36,%37,%38,%39,%40,%41,%42,%43,%44,%45,%46,%47,%48,%49,%50,%51,%52,%53,%54,%55,%56,%57,%58,%59,%60,%61,%62,%63}"
#define PRED_TRUE "{\n.reg .pred p;\nsetp.eq.b32 p, 0, 0;\n"
#define PRED_FALSE "{\n.reg .pred p;\nsetp.ne.b32 p, 0, 0;\n"
__device__ __forceinline__ void fence_acc(float* d) { asm volatile("" : ACC32(d, 0), ACC32(d, 32) :: "memory"); }
template <bool ACCUM>
__device__ __forceinline__ void wgmma_rs(float* d, uint32_t a0, uint32_t a1, uint32_t a2, uint32_t a3, uint64_t db) {
    if (ACCUM)
        asm volatile(PRED_TRUE "wgmma.mma_async.sync.aligned.m64n128k16.f32.bf16.bf16 " REG64 ", {%64,%65,%66,%67}, %68, p, 1, 1, 1;\n}"
                     : ACC32(d, 0), ACC32(d, 32) : "r"(a0), "r"(a1), "r"(a2), "r"(a3), "l"(db));
    else
        asm volatile(PRED_FALSE "wgmma.mma_async.sync.aligned.m64n128k16.f32.bf16.bf16 " REG64 ", {%64,%65,%66,%67}, %68, p, 1, 1, 1;\n}"
                     : OUT32(d, 0), OUT32(d, 32) : "r"(a0), "r"(a1), "r"(a2), "r"(a3), "l"(db));
}
template <bool ACCUM>
__device__ __forceinline__ void wgmma_ss(float* d, uint64_t da, uint64_t db) {
    if (ACCUM)
        asm volatile(PRED_TRUE "wgmma.mma_async.sync.aligned.m64n128k16.f32.bf16.bf16 " REG64 ", %64, %65, p, 1, 1, 0, 1;\n}"
                     : ACC32(d, 0), ACC32(d, 32) : "l"(da), "l"(db));
    else
        asm volatile(PRED_FALSE "wgmma.mma_async.sync.aligned.m64n128k16.f32.bf16.bf16 " REG64 ", %64, %65, p, 1, 1, 0, 1;\n}"
                     : OUT32(d, 0), OUT32(d, 32) : "l"(da), "l"(db));
}
#define REG36 "{%0,%1,%2,%3,%4,%5,%6,%7,%8,%9,%10,%11,%12,%13,%14,%15,%16,%17,%18,%19,%20,%21,%22,%23,%24,%25,%26,%27,%28,%29,%30,%31,%32,%33,%34,%35}"
template <bool ACCUM>
__device__ __forceinline__ void wgmma_tt_n72(float* d, uint64_t da, uint64_t db) {
    if (ACCUM)
        asm volatile(PRED_TRUE "wgmma.mma_async.sync.aligned.m64n72k16.f32.bf16.bf16 " REG36 ", %36, %37, p, 1, 1, 1, 1;\n}"
                     : ACC32(d, 0), "+f"(d[32]), "+f"(d[33]), "+f"(d[34]), "+f"(d[35]) : "l"(da), "l"(db));
    else
        asm volatile(PRED_FALSE "wgmma.mma_async.sync.aligned.m64n72k16.f32.bf16.bf16 " REG36 ", %36, %37, p, 1, 1, 1, 1;\n}"
                     : OUT32(d, 0), "=f"(d[32]), "=f"(d[33]), "=f"(d[34]), "=f"(d[35]) : "l"(da), "l"(db));
}
__device__ __forceinline__ void wgmma_rs_n24(float* d, uint32_t a0, uint32_t a1, uint32_t a2, uint32_t a3, uint64_t db) {
    asm volatile("{\n.reg .pred p;\nsetp.ne.b32 p, 0, 0;\n"
                 "wgmma.mma_async.sync.aligned.m64n24k16.f32.bf16.bf16 {%0,%1,%2,%3,%4,%5,%6,%7,%8,%9,%10,%11}, {%12,%13,%14,%15}, %16, p, 1, 1, 1;\n}"
                 : "=f"(d[0]), "=f"(d[1]), "=f"(d[2]), "=f"(d[3]), "=f"(d[4]), "=f"(d[5]), "=f"(d[6]), "=f"(d[7]), "=f"(d[8]), "=f"(d[9]), "=f"(d[10]), "=f"(d[11])
                 : "r"(a0), "r"(a1), "r"(a2), "r"(a3), "l"(db));
}

__device__ __forceinline__ uint32_t frag_addr(int w, int lane) {
    const int row = 16 * w + (lane & 15);
    return row * 128 + ((((lane >> 4) ^ row) & 7) << 4);
}
__device__ __forceinline__ void stage_block(uint32_t addr, const uint32_t* pk) {
#pragma unroll
    for (int b = 0; b < 8; b += 2) stsm4(addr ^ (b << 4), pk[2 * b], pk[2 * b + 1], pk[2 * b + 2], pk[2 * b + 3]);
}

__device__ __forceinline__ int gu_chunk(int t, int jj) { return (t == 4 ? 10 : 4 * (t - 1)) + jj; }
__device__ __forceinline__ int stage_chunk(int n) { return n < 10 ? n : (n < 14 ? n + 4 : (n < 18 ? n - 4 : n - 4 - ASYM)); }

struct TileSrc { const CUtensorMap* ma; const CUtensorMap* mb; int ca, cb; };
__device__ __forceinline__ TileSrc tile_src(const Params& p, int t, int s, int jj) {
    TileSrc r;
    if (t == 0) { r.ma = r.mb = &p.wqkv; r.ca = 512 + 64 * (4 * s + jj); r.cb = r.ca + 512; }
    else if (t == 3) { r.ma = &p.wq32; r.mb = &p.wg32; r.ca = 64 * (4 * s + jj); r.cb = 896 * s + 512 + 32 * jj; }
    else { r.ma = &p.wg; r.mb = &p.wu; r.ca = r.cb = 896 * s + 64 * gu_chunk(t, jj); }
    return r;
}
__device__ __forceinline__ void issue_w(const Params& p, uint32_t sb, const TileSrc& ts, int slot, int ks, bool split) {
    const uint32_t bar = sb + BAR_FULL + 8 * slot, dst = sb + slot * SLOT_BYTES;
    mbar_expect_tx(bar, SLOT_BYTES);
    tma_ld2(dst, ts.ma, bar, ts.ca, ks * 64);
    tma_ld2(dst + 8192, ts.mb, bar, ts.cb, ks * 64);
    if (split) {
        tma_ld2(dst + 4096, ts.ma, bar, ts.ca + 32, ks * 64);
        tma_ld2(dst + 12288, &p.wu32, bar, ts.cb, ks * 64);
    }
}

__device__ __forceinline__ uint32_t poll_flags(const uint32_t* fp, uint32_t fv, uint32_t target, uint32_t need) {
    uint32_t ready = __ballot_sync(0xffffffffu, (int)(fv - target) >= 0);
    int it = 0;
    while ((ready & need) != need) {
        ready = __ballot_sync(0xffffffffu, (int)(ld_relaxed(fp) - target) >= 0);
        spin_guard(++it);
    }
    asm volatile("fence.acquire.gpu;" ::: "memory");
    fence_async_global();
    return ready;
}

__device__ __forceinline__ void producer(const Params& p, uint32_t sb, int pb, int lane, int i, int s, int jj, int i2, int s2, int c2) {
    const uint32_t epoch = ld_relaxed(&p.scr->epoch[0]);
    int slot = pb, par = 0;
#pragma unroll 1
    for (int t = 0; t < 5; t++) {
        const TileSrc ts = tile_src(p, t, s, jj);
#pragma unroll 1
        for (int ks = (t == 0 ? 4 : 0) + pb; ks < 8; ks += 2) {
            mbar_wait(sb + BAR_EMPTY + 8 * slot, par);
            if (elect_one()) issue_w(p, sb, ts, slot, ks, t == 3);
            __syncwarp();
            slot += 2;
            if (slot >= NSLOT) { slot -= NSLOT; par ^= 1; }
        }
        if (pb == 1 && t == 1) {
            const int wid = (i * 2 + s) * 4 + jj;
            const char* base = lane < 14 ? (const char*)p.wd_ptr + (size_t)wid * 14336 + lane * 1024
                                         : (const char*)p.wo_ptr + (size_t)wid * 4096 + (lane - 14) * 1024;
            if (lane < 18) asm volatile("cp.async.bulk.prefetch.L2.global [%0], 1024;" :: "l"(base) : "memory");
        }
    }
    const uint32_t* fp = &p.scr->hflag[lane < 18 ? (i2 * 2 + s2) * 32 + lane : (i2 * 2 + (s2 ^ 1)) * 32 + 14 - ASYM + ((lane - 18) & 3)];
    const uint32_t ftarget = ((lane >> 1) == 4 ? 4u : 2u) * (epoch + 1);
    uint32_t ready = pb ? ~0u : 0u, fv = ld_relaxed(fp);
    int m = 0;
#pragma unroll 1
    for (int n = 0; n < NSTAGE; n++) {
        const int ch = stage_chunk(n);
        const int sh = n >= 18 ? s2 ^ 1 : s2;
        const uint32_t need = 1u << (n >= 18 ? n : ch);
        if (!(ready & need)) ready = poll_flags(fp, fv, ftarget, need);
        if (n == 6 || n == 12) fv = ld_relaxed(fp);
        mbar_wait(sb + BAR_EMPTY + 16 * m + ((pb == 1 && n < 6) ? 8 : 0), par);
        if (elect_one()) {
            const uint32_t bar = sb + BAR_FULL + 16 * m, dst = sb + (2 * m + pb) * SLOT_BYTES;
            const int k0 = ch < 14 ? 896 * sh + 64 * ch : 256 * sh + 64 * (ch - 14);
            if (pb == 0) {
                const bool solo = n >= NSHARED;
                const int hf = solo ? s2 ^ 1 : 0;
                mbar_expect_tx(bar, solo ? SLOT_BYTES + 8192 : 2 * SLOT_BYTES);
                tma_ld2(dst + hf * 8192, solo ? &p.h64 : &p.h128, bar, ch < 14 ? k0 : FF + k0, 128 * i2 + 64 * hf);
            } else {
                const CUtensorMap* mb = ch < 14 ? &p.wd : &p.wo;
                tma_ld2(dst, mb, bar, 128 * c2, k0);
                tma_ld2(dst + 8192, mb, bar, 128 * c2 + 64, k0);
            }
        }
        __syncwarp();
        if (++m == 6) { m = 0; par ^= 1; }
    }
}

__device__ __forceinline__ void store_warp(const Params& p, uint32_t sb, int lane, int wg, int i, int s, int jj, int i2, int s2, int c2) {
    const uint32_t epoch = ld_relaxed(&p.scr->epoch[0]);
    const uint32_t stg = sb + OFF_STG + wg * 16384;
    if (wg == 1) {
        mbar_wait(sb + BAR_STG_FULL + 8, 0);
        if (elect_one()) {
            mbar_arrive(sb + BAR_STG_EMPTY);
            mbar_arrive(sb + BAR_STG_EMPTY + 8);
            red_release(&p.scr->kvflag[(4 * s + jj) * 32], 1);
        }
        __syncwarp();
    }
#pragma unroll 1
    for (int t = 1; t < 5; t++) {
        mbar_wait(sb + BAR_STG_FULL + 8 * wg, (t - 1 + wg) & 1);
        const int n = t == 3 ? 14 + jj : gu_chunk(t, jj);
        fence_async_smem();
        if (elect_one()) {
            tma_st2(&p.h64, stg, t == 3 ? FF + 256 * s + 64 * jj : 896 * s + 64 * n, 128 * i + 64 * wg);
            if (t == 3) tma_st2(&p.h32, stg + 12288, 896 * s + 512 + 32 * jj, 128 * i + 64 * wg);
            bulk_commit(); bulk_wait0();
            mbar_arrive(sb + BAR_STG_EMPTY + 8 * wg);
            uint32_t* hf = &p.scr->hflag[(i * 2 + s) * 32];
            asm volatile("red.relaxed.gpu.global.add.u32 [%0], 1;" :: "l"(hf + n) : "memory");
            if (t == 3) asm volatile("red.relaxed.gpu.global.add.u32 [%0], 1;" :: "l"(hf + 8 + (jj >> 1)) : "memory");
            if (t == 4 && wg == 0) {
                mbar_expect_tx(sb + BAR_XR, SLOT_BYTES);
                tma_ld2(stg, &p.x2, sb + BAR_XR, 128 * c2, 128 * i2 + 64 * s2);
                tma_ld2(stg + 8192, &p.x2, sb + BAR_XR, 128 * c2 + 64, 128 * i2 + 64 * s2);
            }
        }
        __syncwarp();
        if (t == 2) {
            wait_flag(&p.scr->kviflag[(4 * s + jj) * 32], epoch + 1);
            fence_async_global();
            if (elect_one()) {
                mbar_expect_tx(sb + BAR_KVI + 8 * wg, 3072);
                bulk_ld(stg + 8192, p.scr->kvi + (4 * s + jj) * 4 * 192, 3072, sb + BAR_KVI + 8 * wg);
            }
            __syncwarp();
        }
        if (t == 4 && wg == 1) {
            asm volatile("barrier.cluster.wait.aligned;" ::: "memory");
            if (elect_one()) {
                mbar_expect_tx(sb + BAR_XCH, SLOT_BYTES);
                asm volatile("mbarrier.arrive.shared::cluster.b64 _, [%0];" :: "r"(map_peer(sb + BAR_PEER, s2 ^ 1)) : "memory");
            }
            __syncwarp();
        }
    }
}

__device__ __forceinline__ void issue_x(const __nv_bfloat16* x, uint32_t sb, int wg, int w, int lane, int i) {
    const int r0 = lane >> 4, ch = lane & 15;
    const __nv_bfloat16* src = x + (size_t)(128 * i + 64 * wg + 16 * w + r0) * DM + ch * 8;
    const uint32_t dst = sb + wg * 4 * SLOT_BYTES + (ch >> 3) * 8192 + (16 * w + r0) * 128 + (((ch & 7) ^ r0) << 4);
#pragma unroll 1
    for (int q = 0; q < 4; q++) {
#pragma unroll
        for (int r = 0; r < 8; r++) cp_async16((dst + q * SLOT_BYTES + r * 256) ^ (((2 * r) & 7) << 4), src + r * 2 * DM + q * 128);
        cp_commit();
    }
}

__device__ __forceinline__ void kv_product(const Params& p, float* acc, int w, int lane, int i, int j) {
    wg_fence();
#pragma unroll
    for (int kk = 0; kk < 8; kk++) {
        const uint32_t base = OFF_STG + (kk >> 2) * 16384 + (kk & 3) * 2048;
        const uint64_t da = desc_b(base), db = desc_b(base + 8192, OFF_ONES - (base + 8192));
        if (kk == 0) wgmma_tt_n72<false>(acc, da, db); else wgmma_tt_n72<true>(acc, da, db);
    }
    wg_commit();
    wg_wait<0>();
    asm volatile("" : ACC32(acc, 0), "+f"(acc[32]), "+f"(acc[33]), "+f"(acc[34]), "+f"(acc[35]) :: "memory");
    float c[8];
#pragma unroll
    for (int e = 0; e < 8; e++) {
        const float lo = (w & 1) ? acc[8 + e] : acc[e], hi = (w & 1) ? acc[24 + e] : acc[16 + e];
        c[e] = (w & 2) ? hi : lo;
    }
    float4* dst = p.scr->kvp + (size_t)((j * 16 + i) * 4 + w) * 64;
    dst[lane] = make_float4(c[0], c[1], c[2], c[3]);
    dst[32 + lane] = make_float4(c[4], c[5], c[6], c[7]);
    if ((lane & 3) == 0) {
        float* zd = p.scr->zp + (j * 16 + i) * 64 + w * 16 + (lane >> 2);
        zd[0] = acc[32];
        zd[8] = acc[34];
    }
}

__device__ __forceinline__ void attention_heads(uint32_t* pq, uint32_t img) {
    float d[48];
    wg_fence();
#pragma unroll
    for (int h = 0; h < 4; h++) {
        const uint64_t db = (uint64_t)(((img + h * 768) >> 4) + ((384u >> 4) << 16)) | ((128ull >> 4) << 32);
        wgmma_rs_n24(d + 12 * h, pq[4 * h], pq[4 * h + 1], pq[4 * h + 2], pq[4 * h + 3], db);
    }
    wg_commit();
    wg_wait<0>();
    asm volatile("" : ACC8(d, 0), ACC8(d, 8), ACC8(d, 16) :: "memory");
    asm volatile("" : ACC8(d, 24), ACC8(d, 32), ACC8(d, 40) :: "memory");
#pragma unroll
    for (int h = 0; h < 4; h++) {
        const float* e = d + 12 * h;
        const float r0 = rcp(e[8] + 1e-6f), r1 = rcp(e[10] + 1e-6f);
        pq[4 * h + 0] = pack2(e[0] * r0, e[1] * r0);
        pq[4 * h + 1] = pack2(e[2] * r1, e[3] * r1);
        pq[4 * h + 2] = pack2(e[4] * r0, e[5] * r0);
        pq[4 * h + 3] = pack2(e[6] * r1, e[7] * r1);
    }
}

__device__ __forceinline__ void consumer(const Params& p, uint32_t sb, int wg, int w, int lane, int i, int s, int jj, int i2, int s2, int c2) {
    uint32_t xa[128];
    float acc[64];
    const uint32_t fa = frag_addr(w, lane);
    uint32_t rh0, rh1, nn0, nn1;
    {
        bar_sync(0, 384);
        const uint32_t xs = sb + wg * 4 * SLOT_BYTES + fa;
        float su[2][4], sq[2][4];
#pragma unroll
        for (int e = 0; e < 8; e++) su[e >> 2][e & 3] = sq[e >> 2][e & 3] = 0.f;
#pragma unroll
        for (int q = 0; q < 4; q++) {
            if (q == 0) cp_wait<3>(); else if (q == 1) cp_wait<2>(); else if (q == 2) cp_wait<1>(); else cp_wait<0>();
            __syncwarp();
            if (q == 0 && wg == 0) bar_arrive(7, 160);
#pragma unroll
            for (int o = 8 * q; o < 8 * q + 8; o++)
                ldsm4(xa[4 * o], xa[4 * o + 1], xa[4 * o + 2], xa[4 * o + 3], (xs + (o >> 2) * 8192) ^ ((o & 3) << 5));
            __syncwarp();
            if (lane == 0) mbar_arrive2(sb + BAR_EMPTY + 8 * (4 * wg + q));
            uint32_t z[16];
#pragma unroll
            for (int e = 0; e < 16; e++) {
                const uint32_t* y = xa + 32 * q + 4 * (e >> 1) + (e & 1);
                z[e] = hfma2(y[2], y[2], hmul2(y[0], y[0]));
            }
            fence16(z);
#pragma unroll
            for (int o = 0; o < 8; o++) {
                const uint32_t* y = xa + 32 * q + 4 * o;
                mma16816(su[o & 1], y[0], y[1], y[2], y[3], 0x3F803F80u, 0x3F803F80u);
                if (o < 4) mma16816(sq[o & 1], z[4 * o], z[4 * o + 1], z[4 * o + 2], z[4 * o + 3], 0x3F803F80u, 0x3F803F80u);
            }
        }
        float m0 = (su[0][0] + su[1][0]) * (1.f / DM), m1 = (su[0][2] + su[1][2]) * (1.f / DM);
        float v0 = (sq[0][0] + sq[1][0]) * (1.f / DM) - m0 * m0, v1 = (sq[0][2] + sq[1][2]) * (1.f / DM) - m1 * m1;
        if (__any_sync(0xffffffffu, m0 * m0 > 16.f * v0 || m1 * m1 > 16.f * v1)) {
            const uint4* xr = (const uint4*)(p.x + (size_t)(128 * i + 64 * wg + 16 * w + (lane >> 2)) * DM) + (lane & 3);
            v0 = v1 = 0.f;
#pragma unroll 1
            for (int k = 0; k < 64; k += 4) {
                const uint4 a = __ldg(xr + k), b = __ldg(xr + 8 * (DM / 8) + k);
                const uint32_t ua[4] = {a.x, a.y, a.z, a.w}, ub[4] = {b.x, b.y, b.z, b.w};
#pragma unroll
                for (int e = 0; e < 4; e++) {
                    const float a0 = bf_lo(ua[e]) - m0, a1 = bf_hi(ua[e]) - m0, b0 = bf_lo(ub[e]) - m1, b1 = bf_hi(ub[e]) - m1;
                    v0 = fmaf(a0, a0, fmaf(a1, a1, v0));
                    v1 = fmaf(b0, b0, fmaf(b1, b1, v1));
                }
            }
            v0 += __shfl_xor_sync(0xffffffffu, v0, 1); v1 += __shfl_xor_sync(0xffffffffu, v1, 1);
            v0 += __shfl_xor_sync(0xffffffffu, v0, 2); v1 += __shfl_xor_sync(0xffffffffu, v1, 2);
            v0 *= (1.f / DM); v1 *= (1.f / DM);
            const uint32_t c0 = pack2(-m0, -m0), c1 = pack2(-m1, -m1);
#pragma unroll
            for (int o = 0; o < 128; o += 2) { xa[o] = hadd2(xa[o], c0); xa[o + 1] = hadd2(xa[o + 1], c1); }
            m0 = m1 = 0.f;
        }
        float r0, r1;
        asm("rsqrt.approx.ftz.f32 %0, %1;" : "=f"(r0) : "f"(fmaxf(v0, 0.f) + 1e-5f));
        asm("rsqrt.approx.ftz.f32 %0, %1;" : "=f"(r1) : "f"(fmaxf(v1, 0.f) + 1e-5f));
        rh0 = pack2(r0, r0); rh1 = pack2(r1, r1);
        const float n0 = -m0 * bf_lo(rh0), n1 = -m1 * bf_lo(rh1);
        nn0 = pack2(n0, n0); nn1 = pack2(n1, n1);
#pragma unroll
        for (int o = 0; o < 16; o += 2) {
            xa[o] = hfma2(xa[o], rh0, nn0);
            xa[o + 1] = hfma2(xa[o + 1], rh1, nn1);
        }
    }

    const uint32_t sa = sb + OFF_STG + wg * 16384 + fa;
    int slot = 8, par = 0;
    bool ok = false;
#pragma unroll 1
    for (int t = 0; t < 5; t++) {
        int prev = 0;
        const uint32_t dhi = t == 3 ? ((512u >> 4) | (2u << 30)) : DESC_HI;
        const uint32_t dlo = (SM0 >> 4) + (t == 3 ? (4096u >> 4) << 16 : (8192u >> 4) << 16), kstep = t == 3 ? 64 : 128;
        if (t + wg > 0) bar_sync(1 + wg, 256);
#pragma unroll
        for (int ks = 0; ks < 8; ks++) {
            if (!ok) mbar_wait(sb + BAR_FULL + 8 * slot, par);
            const int nslot = slot + 1 == NSLOT ? 0 : slot + 1, npar = slot + 1 == NSLOT ? par ^ 1 : par;
            wg_fence();
#pragma unroll
            for (int kk = 0; kk < 4; kk++) {
                const int o = (ks * 4 + kk) * 4;
                const uint64_t db = ((uint64_t)dhi << 32) | (dlo + slot * (SLOT_BYTES >> 4) + kk * kstep);
                if (kk == 1) ok = mbar_test(sb + BAR_FULL + 8 * nslot, npar);
                if ((ks | kk) == 0) wgmma_rs<false>(acc, xa[o], xa[o + 1], xa[o + 2], xa[o + 3], db);
                else wgmma_rs<true>(acc, xa[o], xa[o + 1], xa[o + 2], xa[o + 3], db);
            }
            wg_commit();
            if (ks == 7) bar_arrive(2 - wg, 256);
            if (ks < 7 && t == 0) {
#pragma unroll
                for (int o = 16 + 16 * ks; o < 32 + 16 * ks; o += 2) {
                    xa[o] = hfma2(xa[o], rh0, nn0);
                    xa[o + 1] = hfma2(xa[o + 1], rh1, nn1);
                }
            }
            if (ks > 0) {
                wg_wait<1>();
                if (lane == 0) mbar_arrive(sb + BAR_EMPTY + 8 * prev);
            }
            prev = slot;
            slot = nslot; par = npar;
        }
        wg_wait<0>();
        if (lane == 0) mbar_arrive(sb + BAR_EMPTY + 8 * prev);
        fence_acc(acc);
        if (t == 3) {
            uint32_t pq[16], ph[8];
#pragma unroll
            for (int q = 0; q < 8; q++) ph[q] = pack2(acc[32 + 2 * q] * acc[48 + 2 * q], acc[33 + 2 * q] * acc[49 + 2 * q]);
#pragma unroll
            for (int q = 0; q < 16; q++) pq[q] = pack2(phi(acc[2 * q]), phi(acc[2 * q + 1]));
            mbar_wait(sb + BAR_KVI + 8 * wg, 0);
            {
                const int row = 16 * w + (lane & 15);
                const uint32_t ha = sb + OFF_STG + wg * 16384 + 12288 + row * 64 + ((((lane >> 4) ^ (row >> 1)) & 3) << 4);
                stsm4(ha, ph[0], ph[1], ph[2], ph[3]);
                stsm4(ha ^ 32, ph[4], ph[5], ph[6], ph[7]);
            }
            const uint32_t img = SM0 + OFF_STG + wg * 16384 + 8192;
            attention_heads(pq, img);
            stage_block(sa, pq);
        } else if (t == 0) {
            uint32_t pk[16];
#pragma unroll
            for (int q = 0; q < 16; q++) pk[q] = pack2(phi(acc[2 * q]), phi(acc[2 * q + 1]));
            stage_block(sa, pk);
#pragma unroll
            for (int q = 0; q < 16; q++) pk[q] = pack2(acc[32 + 2 * q], acc[33 + 2 * q]);
            stage_block(sa + 8192, pk);
            fence_async_smem();
            if (wg == 0) bar_arrive(5, 256);
            else { bar_sync(5, 256); kv_product(p, acc, w, lane, i, 4 * s + jj); }
        } else {
            uint32_t pk[16];
#pragma unroll
            for (int q = 0; q < 16; q++) pk[q] = pack2(acc[2 * q] * acc[32 + 2 * q], acc[2 * q + 1] * acc[33 + 2 * q]);
            mbar_wait(sb + BAR_STG_EMPTY + 8 * wg, (t - 1) & 1);
            stage_block(sa, pk);
        }
        __syncwarp();
        if (lane == 0 && t + wg > 0) mbar_arrive(sb + BAR_STG_FULL + 8 * wg);
    }

    const int half = wg ^ s2;
    const uint32_t xch = sb + OFF_STG + 16384 + (w * 32 + lane) * 16;
    uint32_t pk[32];
    if (wg == 0) bar_sync(1, 256);
    {
        const int nst = wg ? NSTAGE : NSHARED;
        const uint32_t ao = half * 8192;
        uint32_t ph = 0;
        ok = false;
        mbar_wait(sb + BAR_FULL, 0);
        wg_fence();
        wgmma_ss<false>(acc, desc_a(ao), desc_b(SLOT_BYTES));
#pragma unroll
        for (int kk = 1; kk < 4; kk++) wgmma_ss<true>(acc, desc_a(ao + kk * 32), desc_b(SLOT_BYTES + kk * 2048));
        wg_commit();
#pragma unroll 1
        for (int n0 = 0; n0 < nst; n0 += 6) {
#pragma unroll
            for (int m = 0; m < 6; m++) {
                const int n = n0 + m;
                if (n < nst && n > 0) {
                    if (m == (NSHARED - LEAD) % 6 && n == NSHARED - LEAD && wg == 1) bar_sync(6, 256);
                    if (!ok) mbar_wait(sb + BAR_FULL + 16 * m, ph);
                    wg_fence();
#pragma unroll
                    for (int kk = 0; kk < 4; kk++) {
                        if (kk == 1) ok = mbar_test(sb + BAR_FULL + 16 * ((m + 1) % 6), m == 5 ? ph ^ 1 : ph);
                        wgmma_ss<true>(acc, desc_a(ao + m * 2 * SLOT_BYTES + kk * 32), desc_b((2 * m + 1) * SLOT_BYTES + kk * 2048));
                    }
                    wg_commit();
                    if (m == (NSHARED - 1) % 6 && n == NSHARED - 1 && wg == 0) bar_arrive(6, 256);
                    if (m == 5 && n == 5 && wg == 0) {
                        mbar_wait(sb + BAR_XR, 0);
                        wg_wait<0>();
                        fence_acc(acc);
#pragma unroll
                        for (int b = 0; b < 8; b++) {
                            uint32_t r[4];
                            ldsm4(r[0], r[1], r[2], r[3], (sa + (b >> 2) * 8192) ^ ((b & 3) << 5));
#pragma unroll
                            for (int e = 0; e < 4; e++) {
                                acc[8 * b + 2 * e] += bf_lo(r[e]); acc[8 * b + 2 * e + 1] += bf_hi(r[e]);
                            }
                        }
                        fence_acc(acc);
                        bar_arrive(1, 256);
                    }
                    wg_wait<1>();
                    if (lane == 0 && n + 5 < NSTAGE) {
                        mbar_arrive(sb + BAR_EMPTY + 16 * ((m + 5) % 6));
                        if (n > NSHARED) mbar_arrive(sb + BAR_EMPTY + 16 * ((m + 5) % 6));
                    }
                }
            }
            ph ^= 1;
        }
        if (wg == 1) {
            bar_sync(1, 256);
            mbar_wait_cluster(sb + BAR_XCH, 0);
#pragma unroll
            for (int q = 0; q < 8; q++)
                asm volatile("ld.shared.v4.u32 {%0,%1,%2,%3}, [%4];" : "=r"(pk[4 * q]), "=r"(pk[4 * q + 1]), "=r"(pk[4 * q + 2]), "=r"(pk[4 * q + 3]) : "r"(xch + q * 2048) : "memory");
        }
        wg_wait<0>();
        if (lane == 0 && wg == 0 && NSHARED + 5 < NSTAGE) mbar_arrive(sb + BAR_EMPTY + 16 * ((NSHARED - 1) % 6));
        fence_acc(acc);
    }
    if (wg == 0) {
#pragma unroll
        for (int q = 0; q < 32; q++) pk[q] = pack2(acc[2 * q], acc[2 * q + 1]);
        mbar_wait_cluster(sb + BAR_PEER, 0);
        const uint32_t dst = map_peer(xch, s2 ^ 1), bar = map_peer(sb + BAR_XCH, s2 ^ 1);
#pragma unroll
        for (int q = 0; q < 8; q++) st_async4(dst + q * 2048, pk[4 * q], pk[4 * q + 1], pk[4 * q + 2], pk[4 * q + 3], bar);
    } else {
#pragma unroll
        for (int q = 0; q < 32; q++) pk[q] = hadd2(pack2(acc[2 * q], acc[2 * q + 1]), pk[q]);
        stage_block(sa - 16384, pk);
        stage_block(sa - 8192, pk + 16);
        __syncwarp();
        const int r0 = lane >> 4, ch = lane & 15;
        uint4* dst = (uint4*)(p.outp + (size_t)(128 * i2 + 64 * half + 16 * w + r0) * DM + 128 * c2 + ch * 8);
        const uint32_t ra = sb + OFF_STG + (ch >> 3) * 8192 + (16 * w + r0) * 128 + (((ch & 7) ^ r0) << 4);
        uint4 o[8];
#pragma unroll
        for (int r = 0; r < 8; r++)
            asm volatile("ld.shared.v4.u32 {%0,%1,%2,%3}, [%4];" : "=r"(o[r].x), "=r"(o[r].y), "=r"(o[r].z), "=r"(o[r].w) : "r"((ra + r * 256) ^ (((2 * r) & 7) << 4)) : "memory");
#pragma unroll
        for (int r = 0; r < 8; r++) dst[r * 2 * (DM / 8)] = o[r];
    }
}

__device__ __forceinline__ void aux_consumer(const Params& p, uint32_t sb, int wg, int w, int lane, int a) {
    const uint32_t epoch = ld_relaxed(&p.scr->epoch[0]);
    const int j = 2 * a + wg;
    wait_flag(&p.scr->kvflag[j * 32], 16u * (epoch + 1));
    float4 u0 = make_float4(0.f, 0.f, 0.f, 0.f), u1 = u0;
    float zs = 0.f;
    {
        const uint32_t buf = sb + wg * 4 * SLOT_BYTES, zbuf = sb + OFF_STG + wg * 16384, bar = sb + BAR_FULL + 8 * (8 + 2 * wg);
        fence_async_global();
        if (w == 0 && elect_one()) {
            mbar_expect_tx(bar, 32768 + 4096);
            bulk_ld(zbuf, p.scr->zp + j * 16 * 64, 4096, bar);
            bulk_ld(buf, p.scr->kvp + (size_t)j * 16 * 256, 32768, bar);
            mbar_expect_tx(bar + 8, 32768);
            bulk_ld(buf + 32768, p.scr->kvp + (size_t)j * 16 * 256 + 2048, 32768, bar + 8);
        }
        __syncwarp();
#pragma unroll 1
        for (int b = 0; b < 2; b++) {
            mbar_wait(bar + 8 * b, 0);
#pragma unroll
            for (int q = 0; q < 8; q++) {
                float4 t0, t1;
                const uint32_t a = buf + (b * 8 + q) * 4096 + w * 1024 + lane * 16;
                asm volatile("ld.shared.v4.f32 {%0,%1,%2,%3}, [%4];" : "=f"(t0.x), "=f"(t0.y), "=f"(t0.z), "=f"(t0.w) : "r"(a) : "memory");
                asm volatile("ld.shared.v4.f32 {%0,%1,%2,%3}, [%4];" : "=f"(t1.x), "=f"(t1.y), "=f"(t1.z), "=f"(t1.w) : "r"(a + 512) : "memory");
                u0.x += t0.x; u0.y += t0.y; u0.z += t0.z; u0.w += t0.w;
                u1.x += t1.x; u1.y += t1.y; u1.z += t1.z; u1.w += t1.w;
            }
#pragma unroll
            for (int q = 0; q < 4; q++) {
                float tz;
                asm volatile("ld.shared.f32 %0, [%1];" : "=f"(tz) : "r"(zbuf + (((lane >> 4) * 8 + b * 4 + q) * 64 + w * 16 + (lane & 15)) * 4) : "memory");
                zs += tz;
            }
        }
    }
    zs += __shfl_xor_sync(0xffffffffu, zs, 16);
    const float zv = __shfl_sync(0xffffffffu, zs, lane >> 2), zw = __shfl_sync(0xffffffffu, zs, 8 + (lane >> 2));
    const uint32_t iv[6] = {pack2(u0.x, u0.y), pack2(u1.x, u1.y), pack2(zv, zv), pack2(u0.z, u0.w), pack2(u1.z, u1.w), pack2(zw, zw)};
    const uint32_t simg = sb + OFF_STG + wg * 16384 + 8192;
#pragma unroll
    for (int q = 0; q < 6; q++) asm volatile("st.shared.u32 [%0], %1;" :: "r"(simg + w * 768 + q * 128 + lane * 4), "r"(iv[q]) : "memory");
    bar_sync(3 + wg, 128);
    if (w == 0) {
        fence_async_smem();
        if (elect_one()) {
            asm volatile("cp.async.bulk.global.shared::cta.bulk_group [%0], [%1], 3072;" :: "l"(p.scr->kvi + 4 * j * 192), "r"(simg) : "memory");
            bulk_commit(); bulk_wait0();
            asm volatile("red.relaxed.gpu.global.add.u32 [%0], 1;" :: "l"(&p.scr->kviflag[j * 32]) : "memory");
        }
        __syncwarp();
    }
    if (a == 0 && wg == 0 && w == 0) {
        wait_flag(&p.scr->kviflag[(lane & 7) * 32], epoch + 1);
        if (lane == 0) asm volatile("st.relaxed.gpu.global.u32 [%0], %1;" :: "l"(&p.scr->epoch[0]), "r"(epoch + 1) : "memory");
    }
}

__global__ void __cluster_dims__(2, 1, 1) __launch_bounds__(384, 1) fused_kernel(const __grid_constant__ Params p) {
    extern __shared__ __align__(1024) uint8_t smem_raw[];
    const int warp = __shfl_sync(0xffffffffu, (int)(threadIdx.x >> 5), 0);
    const int lane = lane_id();
    uint32_t smid, rank, sb;
    asm volatile("mov.u32 %0, %%smid;" : "=r"(smid));
    asm volatile("mov.u32 %0, %%cluster_ctarank;" : "=r"(rank));
    asm volatile("mov.u32 %0, %1;" : "=r"(sb) : "r"(smem_u32(smem_raw)));
    const int tpc = smid >> 1;
    int grp, pr;
    if (tpc < 32) { grp = tpc & 7; pr = tpc >> 3; }
    else if (tpc < 60) { const int r = tpc - 32; const int q = r / 7; grp = 1 + r - q * 7; pr = 4 + q; }
    else if (tpc < 62) { grp = -1; pr = tpc - 60; }
    else { grp = 0; pr = 4 + (tpc - 62); }
    const bool worker = grp >= 0;
    const int idx = 2 * pr + rank;
    const int i = 4 * (grp >> 1) + (idx >> 2), s = grp & 1, jj = idx & 3;
    const int i2 = 2 * grp + (pr >> 2), s2 = rank, c2 = pr & 3;

    if (warp >= 8) {
        asm volatile("setmaxnreg.dec.sync.aligned.u32 40;");
        if (warp == 11 && elect_one()) prefetch_map(&p.wqkv);
        __syncwarp();
        if (elect_one()) {
            if (warp == 11) {
#pragma unroll
                for (int q = 8; q < 12; q++) mbar_init(sb + BAR_FULL + 8 * q, 1);
            } else if (warp == 8) {
#pragma unroll
                for (int q = 0; q < NSLOT; q++) mbar_init(sb + BAR_EMPTY + 8 * q, 8);
            } else if (warp == 10) {
#pragma unroll
                for (int q = 0; q < 8; q++) mbar_init(sb + BAR_FULL + 8 * q, 1);
#pragma unroll
                for (int q = 0; q < 8; q++) mbar_arrive(sb + BAR_FULL + 8 * q);
            } else {
                mbar_init(sb + BAR_STG_FULL, 4); mbar_init(sb + BAR_STG_FULL + 8, 4);
#pragma unroll
                for (int q = 0; q < 7; q++) mbar_init(sb + BAR_STG_EMPTY + 8 * q, 1);
            }
            asm volatile("fence.mbarrier_init.release.cluster;" ::: "memory");
        }
        __syncwarp();
        if (warp == 9) {
            if ((sb & 0xffffff) != SM0) asm volatile("trap;");
#pragma unroll
            for (int q = 0; q < 4; q++) asm volatile("st.shared.v4.u32 [%0], {%1, %1, %1, %1};" :: "r"(sb + OFF_ONES + 512 * q + 16 * lane), "r"(0x3F803F80u) : "memory");
            fence_async_smem();
        }
        bar_arrive(0, 384);
        if (warp == 11) {
            const TileSrc ts = tile_src(p, 0, s, jj);
            if (worker) {
                if (elect_one()) issue_w(p, sb, ts, 8, 0, false);
                __syncwarp();
                bar_sync(7, 160);
                if (elect_one()) {
#pragma unroll
                    for (int q = 1; q < 4; q++) issue_w(p, sb, ts, 8 + q, q, false);
                }
                __syncwarp();
            }
        }
        bar_sync(8, 128);
        if (warp == 10) {
            if (elect_one()) {
#pragma unroll
                for (int q = 1; q < 12; q++) prefetch_map(&p.wqkv + q);
            }
            __syncwarp();
        }
        asm volatile("barrier.cluster.arrive.relaxed.aligned;" ::: "memory");
        if (worker) {
            if (warp == 8 || warp == 11) producer(p, sb, warp == 11, lane, i, s, jj, i2, s2, c2);
            else store_warp(p, sb, lane, warp - 9, i, s, jj, i2, s2, c2);
        }
    } else {
        if (worker) issue_x(p.x, sb, warp >> 2, warp & 3, lane, i);
        asm volatile("setmaxnreg.inc.sync.aligned.u32 232;");
        if (!worker) bar_sync(0, 384);
        asm volatile("barrier.cluster.arrive.relaxed.aligned;" ::: "memory");
        if (worker) consumer(p, sb, warp >> 2, warp & 3, lane, i, s, jj, i2, s2, c2);
        else aux_consumer(p, sb, warp >> 2, warp & 3, lane, 2 * pr + rank);
    }
}

typedef __nv_bfloat16 bf16;
__device__ float g_fb_xn[SEQ * DM], g_fb_qkv[SEQ * 3 * DM], g_fb_kv[32 * 272];
__device__ __forceinline__ float fb_phi(float t) { return (t > 0.f ? t + 1.f : expf(t)) + 1e-6f; }
__global__ void fb_ln(const bf16* x) {
    const int r = blockIdx.x * 8 + (threadIdx.x >> 5), l = threadIdx.x & 31;
    float s = 0.f, q = 0.f;
    for (int k = l; k < DM; k += 32) s += (float)x[r * DM + k];
    for (int o = 16; o; o >>= 1) s += __shfl_xor_sync(0xffffffffu, s, o);
    s *= 1.f / DM;
    for (int k = l; k < DM; k += 32) { const float d = (float)x[r * DM + k] - s; q += d * d; }
    for (int o = 16; o; o >>= 1) q += __shfl_xor_sync(0xffffffffu, q, o);
    q = rsqrtf(q * (1.f / DM) + 1e-5f);
    for (int k = l; k < DM; k += 32) g_fb_xn[r * DM + k] = (float)(bf16)(((float)x[r * DM + k] - s) * q);
}
__global__ void fb_proj(const bf16* wqkv, const bf16* wg, const bf16* wu) {
    const int c = blockIdx.x * 256 + threadIdx.x, r = blockIdx.y;
    const float* a = g_fb_xn + r * DM;
    float s = 0.f, t = 0.f;
    if (c < 3 * DM) {
        for (int k = 0; k < DM; k++) s += a[k] * (float)wqkv[k * 3 * DM + c];
        g_fb_qkv[r * 3 * DM + c] = s;
    } else {
        const int f = c - 3 * DM;
        for (int k = 0; k < DM; k++) { s += a[k] * (float)wg[k * FF + f]; t += a[k] * (float)wu[k * FF + f]; }
        g_H[(size_t)r * KH + f] = (bf16)(s * t);
    }
}
__global__ void fb_kv() {
    const int h = blockIdx.x, d = threadIdx.x < 256 ? threadIdx.x >> 4 : threadIdx.x - 256, e = threadIdx.x & 15;
    float s = 0.f;
    for (int t = 0; t < SEQ; t++) {
        const float* row = g_fb_qkv + t * 3 * DM + h * 16;
        s += fb_phi(row[DM + d]) * (threadIdx.x < 256 ? row[2 * DM + e] : 1.f);
    }
    g_fb_kv[h * 272 + threadIdx.x] = s;
}
__global__ void fb_heads() {
    const int r = blockIdx.x, h = threadIdx.x >> 4, e = threadIdx.x & 15;
    float num = 0.f, den = 1e-6f;
    for (int d = 0; d < 16; d++) {
        const float pq = fb_phi(g_fb_qkv[r * 3 * DM + h * 16 + d]);
        num += pq * g_fb_kv[h * 272 + d * 16 + e];
        den += pq * g_fb_kv[h * 272 + 256 + d];
    }
    g_H[(size_t)r * KH + FF + threadIdx.x] = (bf16)(num / den);
}
__global__ void fb_out(const bf16* x, const bf16* wd, const bf16* wo, bf16* out) {
    const int r = blockIdx.x, c = threadIdx.x;
    float s = (float)x[r * DM + c];
    for (int k = 0; k < FF; k++) s += (float)g_H[(size_t)r * KH + k] * (float)wd[k * DM + c];
    for (int k = 0; k < DM; k++) s += (float)g_H[(size_t)r * KH + FF + k] * (float)wo[k * DM + c];
    out[r * DM + c] = (bf16)s;
}

typedef CUresult (*EncodeFn)(CUtensorMap*, CUtensorMapDataType, cuuint32_t, void*, const cuuint64_t*, const cuuint64_t*, const cuuint32_t*,
                             const cuuint32_t*, CUtensorMapInterleave, CUtensorMapSwizzle, CUtensorMapL2promotion, CUtensorMapFloatOOBfill);

void make_map(EncodeFn fn, CUtensorMap* m, const void* ptr, int rank, const cuuint64_t* dims, const cuuint64_t* strides, const cuuint32_t* box) {
    const CUtensorMapSwizzle sw = box[0] == 64 ? CU_TENSOR_MAP_SWIZZLE_128B : CU_TENSOR_MAP_SWIZZLE_64B;
    const cuuint32_t es[3] = {1, 1, 1};
    CUresult r = fn(m, CU_TENSOR_MAP_DATA_TYPE_BFLOAT16, rank, const_cast<void*>(ptr), dims, strides, box, es, CU_TENSOR_MAP_INTERLEAVE_NONE,
                    sw, CU_TENSOR_MAP_L2_PROMOTION_L2_128B, CU_TENSOR_MAP_FLOAT_OOB_FILL_NONE);
    if (r != CUDA_SUCCESS) fprintf(stderr, "tensor map encode failed: %d\n", (int)r);
}
void make_map2(EncodeFn fn, CUtensorMap* m, const void* ptr, uint64_t cols, uint64_t rows, uint32_t box_rows, uint32_t box_cols = 64) {
    const cuuint64_t dims[2] = {cols, rows}, strides[1] = {cols * 2};
    const cuuint32_t box[2] = {box_cols, box_rows};
    make_map(fn, m, ptr, 2, dims, strides, box);
}

}

extern "C" void kernel_launch(void* const* d_in, const int* in_sizes, int n_in, void* d_out, int out_size) {
    (void)in_sizes; (void)n_in; (void)out_size;
    static EncodeFn fn = nullptr;
    static void *pH = nullptr, *pS = nullptr;
    static bool init = false, fused_ok = false;
    if (!init) {
        init = true;
        void* f = nullptr;
        cudaDriverEntryPointQueryResult q;
        cudaGetDriverEntryPoint("cuTensorMapEncodeTiled", &f, cudaEnableDefault, &q);
        fn = (EncodeFn)f;
        cudaGetSymbolAddress(&pH, g_H);
        cudaGetSymbolAddress(&pS, g_scr);
        cudaFuncSetAttribute(fused_kernel, cudaFuncAttributeMaxDynamicSharedMemorySize, SMEM_BYTES);
        int dev = 0, sms = 0, clusters = 0;
        cudaGetDevice(&dev);
        cudaDeviceGetAttribute(&sms, cudaDevAttrMultiProcessorCount, dev);
        cudaLaunchConfig_t cfg = {};
        cfg.gridDim = dim3(NUM_CTAS); cfg.blockDim = dim3(384); cfg.dynamicSmemBytes = SMEM_BYTES;
        cudaLaunchAttribute at;
        at.id = cudaLaunchAttributeClusterDimension; at.val.clusterDim.x = 2; at.val.clusterDim.y = 1; at.val.clusterDim.z = 1;
        cfg.attrs = &at; cfg.numAttrs = 1;
        if (cudaOccupancyMaxActiveClusters(&clusters, fused_kernel, &cfg) != cudaSuccess) { clusters = 0; (void)cudaGetLastError(); }
        fused_ok = fn != nullptr && sms == NUM_CTAS && clusters == NUM_CTAS / 2;
    }
    if (!fused_ok) {
        const bf16 *x = (const bf16*)d_in[0], *wqkv = (const bf16*)d_in[1], *wo = (const bf16*)d_in[2];
        const bf16 *wg = (const bf16*)d_in[4], *wu = (const bf16*)d_in[5], *wd = (const bf16*)d_in[6];
        fb_ln<<<SEQ / 8, 256>>>(x);
        fb_proj<<<dim3(13, SEQ), 256>>>(wqkv, wg, wu);
        fb_kv<<<32, 272>>>();
        fb_heads<<<SEQ, 512>>>();
        fb_out<<<SEQ, 512>>>(x, wd, wo, (bf16*)d_out);
        return;
    }
    Params p;
    make_map2(fn, &p.wqkv, d_in[1], 3 * DM, DM, 64);
    make_map2(fn, &p.wo, d_in[2], DM, DM, 64);
    make_map2(fn, &p.wg, d_in[4], FF, DM, 64);
    make_map2(fn, &p.wu, d_in[5], FF, DM, 64);
    make_map2(fn, &p.wd, d_in[6], DM, FF, 64);
    make_map2(fn, &p.h128, pH, KH, SEQ, 128);
    make_map2(fn, &p.h64, pH, KH, SEQ, 64);
    make_map2(fn, &p.x2, d_in[0], DM, SEQ, 64);
    make_map2(fn, &p.wq32, d_in[1], 3 * DM, DM, 64, 32);
    make_map2(fn, &p.wg32, d_in[4], FF, DM, 64, 32);
    make_map2(fn, &p.wu32, d_in[5], FF, DM, 64, 32);
    make_map2(fn, &p.h32, pH, KH, SEQ, 64, 32);
    p.wo_ptr = (const __nv_bfloat16*)d_in[2];
    p.x = (const __nv_bfloat16*)d_in[0];
    p.wd_ptr = (const __nv_bfloat16*)d_in[6];
    p.outp = (__nv_bfloat16*)d_out;
    p.scr = (Scratch*)pS;
    fused_kernel<<<NUM_CTAS, 384, SMEM_BYTES>>>(p);
}
```
